```python
import torch

def _softmax(x, axis=-1):
    return torch.softmax(x, dim=axis)
def _gelu(x):
    return torch.nn.functional.gelu(x, approximate="tanh")
def _silu(x):
    return torch.nn.functional.silu(x)
def _sigmoid(x):
    return torch.sigmoid(x)
def _layernorm(x, axis=-1, eps=1e-5):
    m = x.mean(dim=axis, keepdim=True)
    v = x.var(dim=axis, keepdim=True, unbiased=False)
    return (x - m) / torch.sqrt(v + eps)
def _scatter_add(tgt, idx, src, axis=0):
    return tgt.clone().index_add_(axis, idx, src)
def _segment_sum(src, seg, n):
    out = torch.zeros((n,) + src.shape[1:], dtype=src.dtype)
    return out.index_add_(0, seg, src)
def _pad(x, pw):
    flat = tuple(v for pair in reversed(pw) for v in pair)
    return torch.nn.functional.pad(x, flat)

kernel_name = 'standalone__channel_attn_cbam__vision'

def setup_inputs():

    _w = (lambda a: (lambda t: t.to(torch.bfloat16) if t.is_floating_point() else t)(torch.as_tensor(a)))
    H = W = 256
    C = 384
    r = max(C // 4, 1)
    return {
        "x": _w((lambda *s: torch.randn(*s, dtype=torch.bfloat16) * 0.1)(1, H, W, C) + (lambda *s: torch.randn(*s, dtype=torch.bfloat16) * 0.1)(1, 1, 1, C) * 2.0),
        "w1": _w((lambda *s: torch.randn(*s, dtype=torch.bfloat16) * 0.1)(C, r)),
        "w2": _w((lambda *s: torch.randn(*s, dtype=torch.bfloat16) * 0.1)(r, C)),
    }

def reference(x, w1, w2):
    B, H, W, C = x.shape
    xf = x.reshape(B, H * W, C)
    gap = torch.mean(xf, 1)
    gmp = torch.amax(xf, 1)
    h_a = gap @ w1
    h_a = h_a * (lambda x, dt: x.to(dt))(h_a > 0, h_a.dtype)
    h_m = gmp @ w1
    h_m = h_m * (lambda x, dt: x.to(dt))(h_m > 0, h_m.dtype)
    scale = _sigmoid(h_a @ w2 + h_m @ w2)
    return x * scale[:, None, None, :]
```

```cpp
#include <cuda_runtime.h>
#include <cuda_bf16.h>
#include <cuda.h>
#include <stdint.h>

namespace {

constexpr int C_TOT   = 384;
constexpr int HID     = 96;
constexpr int ROWS    = 65536;
constexpr int NG      = 6;
constexpr int NRG     = 22;
constexpr int NBLK    = NG * NRG;
constexpr int NT      = 256;
constexpr int CROWS   = 128;
constexpr int CBYTES  = CROWS * 128;
constexpr int NCHUNK  = 23;
constexpr int NREG    = 11;
constexpr int NSLOT   = 12;
constexpr int REM_BASE = NCHUNK * NRG * CROWS;
constexpr int REM_ROWS = 35;
constexpr int NCOPY   = 4;
constexpr int SPIN_LIMIT = 1 << 20;

constexpr int OFF_SLOTS = 0;
constexpr int OFF_REM   = OFF_SLOTS + NSLOT * CBYTES;
constexpr int OFF_W1    = OFF_REM + 4608;
constexpr int OFF_W2    = OFF_W1 + 64 * HID * 2;
constexpr int OFF_RED   = OFF_W2 + HID * 64 * 2;
constexpr int OFF_HS    = OFF_RED + 6144;
constexpr int OFF_BAR   = OFF_HS;
constexpr int OFF_SCALE = OFF_BAR + 192;
constexpr int SMEM_BYTES = OFF_SCALE + 128;
static_assert(SMEM_BYTES <= 232448, "smem");

__device__ ulonglong2 g_part[NG][NRG][32];
__device__ ulonglong2 g_hpart[NCOPY][NG][HID];
__device__ unsigned int g_epoch;
__device__ float g_fb_sum[256][C_TOT];
__device__ float g_fb_max[256][C_TOT];
__device__ __nv_bfloat16 g_fb_scale[C_TOT];

__device__ __forceinline__ uint32_t smem_u32(const void* p) { return (uint32_t)__cvta_generic_to_shared(p); }
__device__ __forceinline__ void mbar_init(uint32_t bar, uint32_t cnt) {
    asm volatile("mbarrier.init.shared::cta.b64 [%0], %1;" ::"r"(bar), "r"(cnt) : "memory");
}
__device__ __forceinline__ void mbar_expect_tx(uint32_t bar, uint32_t bytes) {
    asm volatile("mbarrier.arrive.expect_tx.shared::cta.b64 _, [%0], %1;" ::"r"(bar), "r"(bytes) : "memory");
}
__device__ __forceinline__ bool mbar_try(uint32_t bar, uint32_t parity) {
    uint32_t ok;
    asm volatile("{\n.reg .pred p;\nmbarrier.try_wait.parity.shared::cta.b64 p, [%1], %2;\nselp.u32 %0, 1, 0, p;\n}\n"
                 : "=r"(ok) : "r"(bar), "r"(parity) : "memory");
    return ok != 0;
}
__device__ __forceinline__ void mbar_wait(uint32_t bar, uint32_t parity) {
    int it = 0;
    while (!mbar_try(bar, parity)) { if (++it > SPIN_LIMIT) break; }
}
__device__ __forceinline__ void tma_load_2d(uint32_t dst, const CUtensorMap* tm, uint32_t bar, int c0, int c1, uint64_t pol) {
    asm volatile("cp.async.bulk.tensor.2d.shared::cluster.global.mbarrier::complete_tx::bytes.L2::cache_hint [%0], [%1, {%3, %4}], [%2], %5;"
                 ::"r"(dst), "l"((uint64_t)tm), "r"(bar), "r"(c0), "r"(c1), "l"(pol) : "memory");
}
__device__ __forceinline__ uint4 lds128(uint32_t a) {
    uint4 v;
    asm volatile("ld.shared.v4.u32 {%0,%1,%2,%3}, [%4];" : "=r"(v.x), "=r"(v.y), "=r"(v.z), "=r"(v.w) : "r"(a));
    return v;
}
__device__ __forceinline__ void cp_async16(uint32_t dst, const void* src) {
    asm volatile("cp.async.cg.shared.global [%0], [%1], 16;" ::"r"(dst), "l"(src) : "memory");
}
__device__ __forceinline__ ulonglong2 ld_relaxed_2x64(const ulonglong2* p) {
    ulonglong2 v;
    asm volatile("ld.relaxed.gpu.global.v2.b64 {%0,%1}, [%2];" : "=l"(v.x), "=l"(v.y) : "l"(p) : "memory");
    return v;
}
__device__ __forceinline__ void st_relaxed_2x64(ulonglong2* p, unsigned long long a, unsigned long long b) {
    asm volatile("st.relaxed.gpu.global.v2.b64 [%0], {%1,%2};" ::"l"(p), "l"(a), "l"(b) : "memory");
}
__device__ __forceinline__ uint32_t bf2_max(uint32_t a, uint32_t b) {
    uint32_t r;
    asm("max.NaN.bf16x2 %0, %1, %2;" : "=r"(r) : "r"(a), "r"(b));
    return r;
}
__device__ __forceinline__ uint32_t bf2_mul(uint32_t a, uint32_t b) {
    uint32_t r;
    asm("mul.rn.bf16x2 %0, %1, %2;" : "=r"(r) : "r"(a), "r"(b));
    return r;
}
__device__ __forceinline__ float bf_lo(uint32_t w) { return __uint_as_float(w << 16); }
__device__ __forceinline__ float bf_hi(uint32_t w) { return __uint_as_float(w & 0xffff0000u); }
__device__ __forceinline__ float bf_round(float f) { return __bfloat162float(__float2bfloat16_rn(f)); }
__device__ __forceinline__ uint32_t bf_bits(float f) { return (uint32_t)__bfloat16_as_ushort(__float2bfloat16_rn(f)); }

__device__ __forceinline__ void accum(const uint4& v, float (&s)[8], uint32_t (&m)[4]) {
    s[0] += bf_lo(v.x); s[1] += bf_hi(v.x); m[0] = bf2_max(m[0], v.x);
    s[2] += bf_lo(v.y); s[3] += bf_hi(v.y); m[1] = bf2_max(m[1], v.y);
    s[4] += bf_lo(v.z); s[5] += bf_hi(v.z); m[2] = bf2_max(m[2], v.z);
    s[6] += bf_lo(v.w); s[7] += bf_hi(v.w); m[3] = bf2_max(m[3], v.w);
}
__device__ __forceinline__ uint4 scale4(const uint4& v, const uint4& sc) {
    uint4 o;
    o.x = bf2_mul(v.x, sc.x); o.y = bf2_mul(v.y, sc.y); o.z = bf2_mul(v.z, sc.z); o.w = bf2_mul(v.w, sc.w);
    return o;
}

#define TIM(i)

__global__ void __launch_bounds__(NT, 1)
cbam_fused_kernel(const __grid_constant__ CUtensorMap tm, const __grid_constant__ CUtensorMap tm_rem,
                  const __nv_bfloat16* __restrict__ w1, const __nv_bfloat16* __restrict__ w2,
                  __nv_bfloat16* __restrict__ out)
{
    extern __shared__ __align__(1024) unsigned char smem[];
    const uint32_t sb = smem_u32(smem);
    const int tid = threadIdx.x, warp = tid >> 5, lane = tid & 31;
    const int g = blockIdx.x % NG, rg = blockIdx.x / NG;
    const uint32_t bar0 = sb + OFF_BAR;
    TIM(0);

    uint64_t pol;
    asm volatile("createpolicy.fractional.L2::evict_first.b64 %0, 1.0;" : "=l"(pol));

    if (warp == 0) {
        if (lane < NCHUNK + 1) mbar_init(bar0 + lane * 8, 1);
        asm volatile("fence.mbarrier_init.release.cluster;" ::: "memory");
        __syncwarp();
        if (lane == 0) {
#pragma unroll 1
            for (int c = 0; c < NSLOT; c++) {
                mbar_expect_tx(bar0 + c * 8, CBYTES);
                tma_load_2d(sb + OFF_SLOTS + c * CBYTES, &tm, bar0 + c * 8, g * 64, (c * NRG + rg) * CROWS, pol);
            }
        }
    }
    {
        const uint4* w1g = reinterpret_cast<const uint4*>(w1 + (size_t)g * 64 * HID);
#pragma unroll
        for (int i = 0; i < 3; i++) cp_async16(sb + OFF_W1 + (tid + i * NT) * 16, w1g + tid + i * NT);
#pragma unroll
        for (int i = 0; i < 3; i++) {
            int q = tid + i * NT;
            cp_async16(sb + OFF_W2 + q * 16, w2 + (size_t)(q >> 3) * C_TOT + g * 64 + (q & 7) * 8);
        }
        asm volatile("cp.async.commit_group;" ::: "memory");
    }
    unsigned int epoch;
    asm volatile("ld.relaxed.gpu.global.u32 %0, [%1];" : "=r"(epoch) : "l"(&g_epoch) : "memory");
    const uint32_t tag = epoch + 1u;
    __syncthreads();

    float s[8];
    uint32_t m[4];
#pragma unroll
    for (int i = 0; i < 8; i++) s[i] = 0.f;
#pragma unroll
    for (int i = 0; i < 4; i++) m[i] = 0xff80ff80u;

    uint4 r[NREG * 4];
    const uint32_t toff = tid * 16;
#pragma unroll
    for (int c = 0; c < NREG; c++) {
        mbar_wait(bar0 + c * 8, 0);
#pragma unroll
        for (int p = 0; p < 4; p++) r[c * 4 + p] = lds128(sb + OFF_SLOTS + c * CBYTES + p * 4096 + toff);
#pragma unroll
        for (int p = 0; p < 4; p++) accum(r[c * 4 + p], s, m);
        __syncthreads();
        if (tid == 0) {
            const int cn = c + NSLOT;
            mbar_expect_tx(bar0 + cn * 8, CBYTES);
            tma_load_2d(sb + OFF_SLOTS + c * CBYTES, &tm, bar0 + cn * 8, g * 64, (cn * NRG + rg) * CROWS, pol);
            if (c == NREG - 1) {
                mbar_expect_tx(bar0 + NCHUNK * 8, REM_ROWS * 128);
                tma_load_2d(sb + OFF_REM, &tm_rem, bar0 + NCHUNK * 8, g * 64, REM_BASE + rg * REM_ROWS, pol);
            }
        }
    }
    asm volatile("cp.async.wait_all;" ::: "memory");
#pragma unroll 1
    for (int c = NREG; c < NCHUNK; c++) {
        const int slot = (c < NSLOT) ? c : c - NSLOT;
        mbar_wait(bar0 + c * 8, 0);
        uint4 v[4];
#pragma unroll
        for (int p = 0; p < 4; p++) v[p] = lds128(sb + OFF_SLOTS + slot * CBYTES + p * 4096 + toff);
#pragma unroll
        for (int p = 0; p < 4; p++) accum(v[p], s, m);
    }
    const int rem_valid = min(REM_ROWS, ROWS - (REM_BASE + rg * REM_ROWS));
    {
        mbar_wait(bar0 + NCHUNK * 8, 0);
        const int r0 = tid >> 3;
        if (r0 < rem_valid) { uint4 v = lds128(sb + OFF_REM + toff); accum(v, s, m); }
        if (r0 + 32 < rem_valid) { uint4 v = lds128(sb + OFF_REM + 4096 + toff); accum(v, s, m); }
    }
    TIM(1);

    {
        const bool up = (lane & 16) != 0;
        float k0 = up ? s[4] : s[0], k1 = up ? s[5] : s[1], k2 = up ? s[6] : s[2], k3 = up ? s[7] : s[3];
        float t0 = up ? s[0] : s[4], t1 = up ? s[1] : s[5], t2 = up ? s[2] : s[6], t3 = up ? s[3] : s[7];
        uint32_t km0 = up ? m[2] : m[0], km1 = up ? m[3] : m[1];
        uint32_t tm0 = up ? m[0] : m[2], tm1 = up ? m[1] : m[3];
        k0 += __shfl_xor_sync(~0u, t0, 16); k1 += __shfl_xor_sync(~0u, t1, 16);
        k2 += __shfl_xor_sync(~0u, t2, 16); k3 += __shfl_xor_sync(~0u, t3, 16);
        km0 = bf2_max(km0, __shfl_xor_sync(~0u, tm0, 16));
        km1 = bf2_max(km1, __shfl_xor_sync(~0u, tm1, 16));
        const bool up2 = (lane & 8) != 0;
        float a0 = up2 ? k2 : k0, a1 = up2 ? k3 : k1;
        float b0 = up2 ? k0 : k2, b1 = up2 ? k1 : k3;
        uint32_t am = up2 ? km1 : km0, bm = up2 ? km0 : km1;
        a0 += __shfl_xor_sync(~0u, b0, 8); a1 += __shfl_xor_sync(~0u, b1, 8);
        am = bf2_max(am, __shfl_xor_sync(~0u, bm, 8));
        const int pair = (lane & 7) * 4 + ((lane >> 4) & 1) * 2 + ((lane >> 3) & 1);
        uint4* red = reinterpret_cast<uint4*>(smem + OFF_RED);
        red[warp * 32 + pair] = make_uint4(__float_as_uint(a0), __float_as_uint(a1), am, 0u);
    }
    __syncthreads();
    if (warp == 0) {
        const uint4* red = reinterpret_cast<const uint4*>(smem + OFF_RED);
        float a0 = 0.f, a1 = 0.f; uint32_t am = 0xff80ff80u;
#pragma unroll
        for (int w = 0; w < 8; w++) {
            uint4 v = red[w * 32 + lane];
            a0 += __uint_as_float(v.x); a1 += __uint_as_float(v.y); am = bf2_max(am, v.z);
        }
        const uint32_t t16 = tag << 16;
        unsigned long long p0 = ((unsigned long long)(t16 | (am & 0xffffu)) << 32) | __float_as_uint(a0);
        unsigned long long p1 = ((unsigned long long)(t16 | (am >> 16)) << 32) | __float_as_uint(a1);
        st_relaxed_2x64(&g_part[g][rg][lane], p0, p1);
    }
    TIM(2);

    if (rg == 0) {
        float w1f[8][3];
        {
            const __nv_bfloat16* w1s = reinterpret_cast<const __nv_bfloat16*>(smem + OFF_W1);
#pragma unroll
            for (int c = 0; c < 8; c++)
#pragma unroll
                for (int u = 0; u < 3; u++) w1f[c][u] = __bfloat162float(w1s[(warp * 8 + c) * HID + lane + 32 * u]);
        }
        const int p = lane & 3, rs = lane >> 2;
        const uint32_t t16 = tag & 0xffffu;
        float s0 = 0.f, s1 = 0.f; uint32_t mm = 0xff80ff80u;
        {
            const ulonglong2* src = &g_part[g][rs][warp * 4 + p];
            const bool has3 = (rs + 16) < NRG;
            ulonglong2 v0, v1, v2;
            bool ok0 = false, ok1 = false, ok2 = !has3;
            int it = 0;
            while (true) {
                if (!ok0) v0 = ld_relaxed_2x64(src);
                if (!ok1) v1 = ld_relaxed_2x64(src + 8 * 32);
                if (!ok2) v2 = ld_relaxed_2x64(src + 16 * 32);
                ok0 = ((uint32_t)(v0.x >> 48) == t16) && ((uint32_t)(v0.y >> 48) == t16);
                ok1 = ((uint32_t)(v1.x >> 48) == t16) && ((uint32_t)(v1.y >> 48) == t16);
                if (has3) ok2 = ((uint32_t)(v2.x >> 48) == t16) && ((uint32_t)(v2.y >> 48) == t16);
                if ((ok0 && ok1 && ok2) || ++it > SPIN_LIMIT) break;
            }
            s0 = __uint_as_float((uint32_t)v0.x) + __uint_as_float((uint32_t)v1.x);
            s1 = __uint_as_float((uint32_t)v0.y) + __uint_as_float((uint32_t)v1.y);
            mm = bf2_max(((uint32_t)(v0.x >> 32) & 0xffffu) | ((uint32_t)(v0.y >> 32) << 16),
                         ((uint32_t)(v1.x >> 32) & 0xffffu) | ((uint32_t)(v1.y >> 32) << 16));
            if (has3) {
                s0 += __uint_as_float((uint32_t)v2.x);
                s1 += __uint_as_float((uint32_t)v2.y);
                mm = bf2_max(mm, ((uint32_t)(v2.x >> 32) & 0xffffu) | ((uint32_t)(v2.y >> 32) << 16));
            }
        }
        __syncwarp();
#pragma unroll
        for (int o = 4; o <= 16; o <<= 1) {
            s0 += __shfl_xor_sync(~0u, s0, o);
            s1 += __shfl_xor_sync(~0u, s1, o);
            mm = bf2_max(mm, __shfl_xor_sync(~0u, mm, o));
        }
        const uint32_t gp = bf_bits(s0 * (1.0f / ROWS)) | (bf_bits(s1 * (1.0f / ROWS)) << 16);
        float ha[3] = {0.f, 0.f, 0.f}, hm[3] = {0.f, 0.f, 0.f};
#pragma unroll
        for (int q = 0; q < 4; q++) {
            const uint32_t gq = __shfl_sync(~0u, gp, q);
            const uint32_t mq = __shfl_sync(~0u, mm, q);
            const float g0 = bf_lo(gq), g1 = bf_hi(gq), m0 = bf_lo(mq), m1 = bf_hi(mq);
#pragma unroll
            for (int u = 0; u < 3; u++) {
                ha[u] = fmaf(g0, w1f[2 * q][u], ha[u]); ha[u] = fmaf(g1, w1f[2 * q + 1][u], ha[u]);
                hm[u] = fmaf(m0, w1f[2 * q][u], hm[u]); hm[u] = fmaf(m1, w1f[2 * q + 1][u], hm[u]);
            }
        }
        __syncthreads();
        float2* red2 = reinterpret_cast<float2*>(smem + OFF_RED);
#pragma unroll
        for (int u = 0; u < 3; u++) red2[warp * HID + lane + 32 * u] = make_float2(ha[u], hm[u]);
        __syncthreads();
        if (tid < 2 * HID) {
            const int j = tid % HID, k = tid / HID;
            float a = 0.f, b = 0.f;
#pragma unroll
            for (int w = 0; w < 8; w++) { float2 v = red2[w * HID + j]; a += v.x; b += v.y; }
            unsigned long long pa = ((unsigned long long)tag << 32) | __float_as_uint(a);
            unsigned long long pb = ((unsigned long long)tag << 32) | __float_as_uint(b);
#pragma unroll
            for (int cp = 0; cp < NCOPY / 2; cp++) st_relaxed_2x64(&g_hpart[k * (NCOPY / 2) + cp][g][j], pa, pb);
        }
        __syncthreads();
    }
    TIM(3);

    float w2f[12][2];
    {
        const uint32_t* w2s = reinterpret_cast<const uint32_t*>(smem + OFF_W2);
        const int cp = lane & 3, js = lane >> 2;
#pragma unroll
        for (int i = 0; i < 12; i++) {
            uint32_t w = w2s[(i * 8 + js) * 32 + warp * 4 + cp];
            w2f[i][0] = bf_lo(w); w2f[i][1] = bf_hi(w);
        }
    }
    if (rg != 0) __syncthreads();
    float2* hs = reinterpret_cast<float2*>(smem + OFF_RED);
    if (tid < HID) {
        const ulonglong2* src = &g_hpart[blockIdx.x % NCOPY][0][0];
        {
            int it = 0;
            while (true) {
                bool ok = false;
                if (lane < NG) { ulonglong2 v = ld_relaxed_2x64(src + lane * HID + warp * 32); ok = (uint32_t)(v.x >> 32) == tag; }
                if (__any_sync(~0u, ok) || ++it > SPIN_LIMIT) break;
            }
        }
        ulonglong2 v[NG];
        uint32_t okm = 0;
        int it = 0;
        while (true) {
#pragma unroll
            for (int q = 0; q < NG; q++) if (!((okm >> q) & 1)) v[q] = ld_relaxed_2x64(src + q * HID + tid);
#pragma unroll
            for (int q = 0; q < NG; q++)
                if (((uint32_t)(v[q].x >> 32) == tag) && ((uint32_t)(v[q].y >> 32) == tag)) okm |= 1u << q;
            if (okm == (1u << NG) - 1u || ++it > SPIN_LIMIT) break;
        }
        float a = 0.f, b = 0.f;
#pragma unroll
        for (int q = 0; q < NG; q++) { a += __uint_as_float((uint32_t)v[q].x); b += __uint_as_float((uint32_t)v[q].y); }
        a = bf_round(a); b = bf_round(b);
        a = a * (a > 0.f ? 1.f : 0.f);
        b = b * (b > 0.f ? 1.f : 0.f);
        hs[tid] = make_float2(a, b);
    }
    __syncthreads();
    TIM(4);
    {
        const int js = lane >> 2;
        float za0 = 0.f, za1 = 0.f, zm0 = 0.f, zm1 = 0.f;
#pragma unroll
        for (int i = 0; i < 12; i++) {
            const float2 h = hs[i * 8 + js];
            za0 = fmaf(h.x, w2f[i][0], za0); za1 = fmaf(h.x, w2f[i][1], za1);
            zm0 = fmaf(h.y, w2f[i][0], zm0); zm1 = fmaf(h.y, w2f[i][1], zm1);
        }
        const bool up = (lane & 4) != 0;
        float ka = up ? za1 : za0, km = up ? zm1 : zm0;
        float ta = up ? za0 : za1, tmm = up ? zm0 : zm1;
        ka += __shfl_xor_sync(~0u, ta, 4); km += __shfl_xor_sync(~0u, tmm, 4);
        ka += __shfl_xor_sync(~0u, ka, 8); km += __shfl_xor_sync(~0u, km, 8);
        ka += __shfl_xor_sync(~0u, ka, 16); km += __shfl_xor_sync(~0u, km, 16);
        if (lane < 8) {
            const float z = bf_round(bf_round(ka) + bf_round(km));
            const float sg = 1.0f / (1.0f + __expf(-z));
            __nv_bfloat16* sc = reinterpret_cast<__nv_bfloat16*>(smem + OFF_SCALE);
            sc[warp * 8 + (lane & 3) * 2 + (lane >> 2)] = __float2bfloat16_rn(sg);
        }
    }
    __syncthreads();
    const uint4 sc = lds128(sb + OFF_SCALE + (lane & 7) * 16);
    if (blockIdx.x == 0 && tid == 0) {
        asm volatile("st.relaxed.gpu.global.u32 [%0], %1;" ::"l"(&g_epoch), "r"(tag) : "memory");
    }
    TIM(5);

    uint4* ob = reinterpret_cast<uint4*>(out) + (size_t)(rg * CROWS + (tid >> 3)) * 48 + g * 8 + (tid & 7);
#pragma unroll
    for (int c = 0; c < NREG; c++)
#pragma unroll
        for (int p = 0; p < 4; p++)
            ob[(size_t)(c * NRG * CROWS + p * 32) * 48] = scale4(r[c * 4 + p], sc);
#pragma unroll 1
    for (int c = NREG; c < NCHUNK; c++) {
        const int slot = (c < NSLOT) ? c : c - NSLOT;
        uint4 v[4];
#pragma unroll
        for (int p = 0; p < 4; p++) v[p] = lds128(sb + OFF_SLOTS + slot * CBYTES + p * 4096 + toff);
#pragma unroll
        for (int p = 0; p < 4; p++) ob[(size_t)(c * NRG * CROWS + p * 32) * 48] = scale4(v[p], sc);
    }
    {
        const int r0 = tid >> 3;
        uint4* orem = reinterpret_cast<uint4*>(out) + (size_t)(REM_BASE + rg * REM_ROWS + r0) * 48 + g * 8 + (tid & 7);
        if (r0 < rem_valid) { uint4 v = lds128(sb + OFF_REM + toff); orem[0] = scale4(v, sc); }
        if (r0 + 32 < rem_valid) { uint4 v = lds128(sb + OFF_REM + 4096 + toff); orem[32 * 48] = scale4(v, sc); }
    }
    TIM(6);
}

__global__ void fb_pool_kernel(const __nv_bfloat16* __restrict__ x) {
    const int c = threadIdx.x;
    float s = 0.f; float mx = -INFINITY;
    const __nv_bfloat16* p = x + (size_t)blockIdx.x * 256 * C_TOT + c;
    bool nan = false;
    for (int r = 0; r < 256; r++) { float v = __bfloat162float(p[(size_t)r * C_TOT]); s += v; mx = fmaxf(mx, v); nan |= (v != v); }
    if (nan) mx = __int_as_float(0x7fffffff);
    g_fb_sum[blockIdx.x][c] = s; g_fb_max[blockIdx.x][c] = mx;
}
__global__ void fb_mlp_kernel(const __nv_bfloat16* __restrict__ w1, const __nv_bfloat16* __restrict__ w2) {
    __shared__ float ga[C_TOT], gm[C_TOT], ha[HID], hm[HID];
    const int c = threadIdx.x;
    float s = 0.f, mx = -INFINITY; bool nan = false;
    for (int b = 0; b < 256; b++) { s += g_fb_sum[b][c]; float v = g_fb_max[b][c]; mx = fmaxf(mx, v); nan |= (v != v); }
    if (nan) mx = __int_as_float(0x7fffffff);
    ga[c] = bf_round(s * (1.0f / ROWS)); gm[c] = mx;
    __syncthreads();
    if (c < HID) {
        float a = 0.f, b = 0.f;
        for (int k = 0; k < C_TOT; k++) { float w = __bfloat162float(w1[k * HID + c]); a = fmaf(ga[k], w, a); b = fmaf(gm[k], w, b); }
        a = bf_round(a); b = bf_round(b);
        ha[c] = a * (a > 0.f ? 1.f : 0.f); hm[c] = b * (b > 0.f ? 1.f : 0.f);
    }
    __syncthreads();
    float a = 0.f, b = 0.f;
    for (int j = 0; j < HID; j++) { float w = __bfloat162float(w2[j * C_TOT + c]); a = fmaf(ha[j], w, a); b = fmaf(hm[j], w, b); }
    const float z = bf_round(bf_round(a) + bf_round(b));
    g_fb_scale[c] = __float2bfloat16_rn(1.0f / (1.0f + __expf(-z)));
}
__global__ void fb_scale_kernel(const uint4* __restrict__ x, uint4* __restrict__ out) {
    const size_t n = (size_t)ROWS * 48;
    for (size_t i = blockIdx.x * (size_t)blockDim.x + threadIdx.x; i < n; i += (size_t)gridDim.x * blockDim.x) {
        const uint4 sc = reinterpret_cast<const uint4*>(g_fb_scale)[i % 48];
        out[i] = scale4(x[i], sc);
    }
}

typedef CUresult (*PFN_encodeTiled)(CUtensorMap*, CUtensorMapDataType, cuuint32_t, void*, const cuuint64_t*,
                                    const cuuint64_t*, const cuuint32_t*, const cuuint32_t*, CUtensorMapInterleave,
                                    CUtensorMapSwizzle, CUtensorMapL2promotion, CUtensorMapFloatOOBfill);

}

extern "C" void kernel_launch(void* const* d_in, const int* in_sizes, int n_in, void* d_out, int out_size) {
    const __nv_bfloat16* x  = (const __nv_bfloat16*)d_in[0];
    const __nv_bfloat16* w1 = (const __nv_bfloat16*)d_in[1];
    const __nv_bfloat16* w2 = (const __nv_bfloat16*)d_in[2];
    __nv_bfloat16* out = (__nv_bfloat16*)d_out;
    cudaStream_t stream = cudaStreamPerThread;

    static int mode = -1;
    static PFN_encodeTiled enc = nullptr;
    if (mode < 0) {
        mode = 0;
        int dev = 0, sms = 0, occ = 0;
        cudaGetDevice(&dev);
        cudaDeviceGetAttribute(&sms, cudaDevAttrMultiProcessorCount, dev);
        void* fn = nullptr;
        cudaDriverEntryPointQueryResult qr;
        if (cudaGetDriverEntryPoint("cuTensorMapEncodeTiled", &fn, cudaEnableDefault, &qr) == cudaSuccess && fn &&
            cudaFuncSetAttribute(cbam_fused_kernel, cudaFuncAttributeMaxDynamicSharedMemorySize, SMEM_BYTES) == cudaSuccess &&
            cudaOccupancyMaxActiveBlocksPerMultiprocessor(&occ, cbam_fused_kernel, NT, SMEM_BYTES) == cudaSuccess &&
            occ >= 1 && sms * occ >= NBLK) {
            enc = (PFN_encodeTiled)fn;
            mode = 1;
        }
        (void)cudaGetLastError();
    }
    if (mode == 1) {
        CUtensorMap tm, tmr;
        cuuint64_t gd[2] = {(cuuint64_t)C_TOT, (cuuint64_t)ROWS};
        cuuint64_t gs[1] = {(cuuint64_t)C_TOT * 2};
        cuuint32_t box[2] = {64, (cuuint32_t)CROWS};
        cuuint32_t boxr[2] = {64, (cuuint32_t)REM_ROWS};
        cuuint32_t es[2] = {1, 1};
        CUresult r1 = enc(&tm, CU_TENSOR_MAP_DATA_TYPE_BFLOAT16, 2, (void*)x, gd, gs, box, es, CU_TENSOR_MAP_INTERLEAVE_NONE,
                          CU_TENSOR_MAP_SWIZZLE_NONE, CU_TENSOR_MAP_L2_PROMOTION_L2_128B, CU_TENSOR_MAP_FLOAT_OOB_FILL_NONE);
        CUresult r2 = enc(&tmr, CU_TENSOR_MAP_DATA_TYPE_BFLOAT16, 2, (void*)x, gd, gs, boxr, es, CU_TENSOR_MAP_INTERLEAVE_NONE,
                          CU_TENSOR_MAP_SWIZZLE_NONE, CU_TENSOR_MAP_L2_PROMOTION_L2_128B, CU_TENSOR_MAP_FLOAT_OOB_FILL_NONE);
        if (r1 == CUDA_SUCCESS && r2 == CUDA_SUCCESS) {
            cbam_fused_kernel<<<NBLK, NT, SMEM_BYTES, stream>>>(tm, tmr, w1, w2, out);
            return;
        }
    }
    fb_pool_kernel<<<256, C_TOT, 0, stream>>>(x);
    fb_mlp_kernel<<<1, C_TOT, 0, stream>>>(w1, w2);
    fb_scale_kernel<<<1056, 256, 0, stream>>>((const uint4*)x, (uint4*)out);
}
```

```cpp
#include <cuda_runtime.h>
#include <cuda_bf16.h>
#include <cuda.h>
#include <stdint.h>

namespace {

constexpr int C_TOT   = 384;
constexpr int HID     = 96;
constexpr int ROWS    = 65536;
constexpr int NG      = 6;
constexpr int NRG     = 22;
constexpr int NBLK    = NG * NRG;
constexpr int NT      = 256;
constexpr int CROWS   = 128;
constexpr int NP      = CROWS / 32;
constexpr int CBYTES  = CROWS * 128;
constexpr int NCHUNK  = 23;
constexpr int NREG    = 11;
constexpr int NSLOT   = 12;
constexpr int REM_BASE = NCHUNK * NRG * CROWS;
constexpr int REM_ROWS = 37;
constexpr int NLDG    = 2;
constexpr int KINIT   = 4;
constexpr int KMIN    = 3;
constexpr int KMAX    = 6;
constexpr int NCOPY   = 4;
constexpr int SPIN_LIMIT = 1 << 20;

constexpr int OFF_SLOTS = 0;
constexpr int OFF_REM   = OFF_SLOTS + NSLOT * CBYTES;
constexpr int OFF_W1    = OFF_REM + 6144;
constexpr int OFF_W2    = OFF_W1 + 64 * HID * 2;
constexpr int OFF_RED   = OFF_W2 + HID * 64 * 2;
constexpr int OFF_BAR   = OFF_RED + 4096;
constexpr int OFF_SCALE = OFF_BAR + 192;
constexpr int SMEM_BYTES = OFF_SCALE + 128;
static_assert(SMEM_BYTES <= 232448, "smem");
static_assert(KMAX <= NSLOT - 1, "slot reuse");

__device__ ulonglong2 g_part[NG][NRG][32];
__device__ uint2 g_hpart[NCOPY][NG][HID];
__device__ unsigned int g_epoch;
__device__ float g_fb_sum[256][C_TOT];
__device__ float g_fb_max[256][C_TOT];
__device__ __nv_bfloat16 g_fb_scale[C_TOT];

__device__ __forceinline__ uint32_t smem_u32(const void* p) { return (uint32_t)__cvta_generic_to_shared(p); }
__device__ __forceinline__ void mbar_init(uint32_t bar, uint32_t cnt) {
    asm volatile("mbarrier.init.shared::cta.b64 [%0], %1;" ::"r"(bar), "r"(cnt) : "memory");
}
__device__ __forceinline__ void mbar_expect_tx(uint32_t bar, uint32_t bytes) {
    asm volatile("mbarrier.arrive.expect_tx.shared::cta.b64 _, [%0], %1;" ::"r"(bar), "r"(bytes) : "memory");
}
__device__ __forceinline__ bool mbar_try(uint32_t bar, uint32_t parity) {
    uint32_t ok;
    asm volatile("{\n.reg .pred p;\nmbarrier.try_wait.parity.shared::cta.b64 p, [%1], %2;\nselp.u32 %0, 1, 0, p;\n}\n"
                 : "=r"(ok) : "r"(bar), "r"(parity) : "memory");
    return ok != 0;
}
__device__ __forceinline__ bool mbar_test(uint32_t bar, uint32_t parity) {
    uint32_t ok;
    asm volatile("{\n.reg .pred p;\nmbarrier.test_wait.parity.shared::cta.b64 p, [%1], %2;\nselp.u32 %0, 1, 0, p;\n}\n"
                 : "=r"(ok) : "r"(bar), "r"(parity) : "memory");
    return ok != 0;
}
__device__ __forceinline__ unsigned int gtime() {
    unsigned int t;
    asm volatile("mov.u32 %0, %globaltimer_lo;" : "=r"(t) :: "memory");
    return t;
}
__device__ __forceinline__ void mbar_wait(uint32_t bar, uint32_t parity) {
    int it = 0;
    while (!mbar_try(bar, parity)) { if (++it > SPIN_LIMIT) break; }
}
__device__ __forceinline__ void tma_load_2d(uint32_t dst, const CUtensorMap* tm, uint32_t bar, int c0, int c1, uint64_t pol) {
    asm volatile("cp.async.bulk.tensor.2d.shared::cluster.global.mbarrier::complete_tx::bytes.L2::cache_hint [%0], [%1, {%3, %4}], [%2], %5;"
                 ::"r"(dst), "l"((uint64_t)tm), "r"(bar), "r"(c0), "r"(c1), "l"(pol) : "memory");
}
__device__ __forceinline__ uint4 lds128(uint32_t a) {
    uint4 v;
    asm volatile("ld.shared.v4.u32 {%0,%1,%2,%3}, [%4];" : "=r"(v.x), "=r"(v.y), "=r"(v.z), "=r"(v.w) : "r"(a));
    return v;
}
__device__ __forceinline__ void cp_async16(uint32_t dst, const void* src) {
    asm volatile("cp.async.cg.shared.global [%0], [%1], 16;" ::"r"(dst), "l"(src) : "memory");
}
__device__ __forceinline__ uint4 ldg_stream(const uint4* p, uint64_t pol) {
    uint4 v;
    asm volatile("ld.global.nc.L1::no_allocate.L2::cache_hint.v4.u32 {%0,%1,%2,%3}, [%4], %5;"
                 : "=r"(v.x), "=r"(v.y), "=r"(v.z), "=r"(v.w) : "l"(p), "l"(pol));
    return v;
}
__device__ __forceinline__ void stg_stream(uint4* p, const uint4& v, uint64_t pol) {
    asm volatile("st.global.L2::cache_hint.v4.u32 [%0], {%1,%2,%3,%4}, %5;"
                 ::"l"(p), "r"(v.x), "r"(v.y), "r"(v.z), "r"(v.w), "l"(pol) : "memory");
}
__device__ __forceinline__ void ldp_2x64(ulonglong2& v, const void* p, uint32_t pred) {
    asm volatile("{\n.reg .pred q;\nsetp.ne.u32 q, %3, 0;\n@q ld.relaxed.gpu.global.v2.b64 {%0,%1}, [%2];\n}\n"
                 : "+l"(v.x), "+l"(v.y) : "l"(p), "r"(pred) : "memory");
}
__device__ __forceinline__ void ldp_2x32(uint2& v, const void* p, uint32_t pred) {
    asm volatile("{\n.reg .pred q;\nsetp.ne.u32 q, %3, 0;\n@q ld.relaxed.gpu.global.v2.b32 {%0,%1}, [%2];\n}\n"
                 : "+r"(v.x), "+r"(v.y) : "l"(p), "r"(pred) : "memory");
}
__device__ __forceinline__ void st_relaxed_2x64(void* p, unsigned long long a, unsigned long long b) {
    asm volatile("st.relaxed.gpu.global.v2.b64 [%0], {%1,%2};" ::"l"(p), "l"(a), "l"(b) : "memory");
}
__device__ __forceinline__ void st_relaxed_2x32(void* p, uint32_t a, uint32_t b) {
    asm volatile("st.relaxed.gpu.global.v2.b32 [%0], {%1,%2};" ::"l"(p), "r"(a), "r"(b) : "memory");
}
__device__ __forceinline__ uint32_t bf2_max(uint32_t a, uint32_t b) {
    uint32_t r;
    asm("max.NaN.bf16x2 %0, %1, %2;" : "=r"(r) : "r"(a), "r"(b));
    return r;
}
__device__ __forceinline__ uint32_t bf2_mul(uint32_t a, uint32_t b) {
    uint32_t r;
    asm("mul.rn.bf16x2 %0, %1, %2;" : "=r"(r) : "r"(a), "r"(b));
    return r;
}
__device__ __forceinline__ float bf_lo(uint32_t w) { return __uint_as_float(w << 16); }
__device__ __forceinline__ float bf_hi(uint32_t w) { return __uint_as_float(w & 0xffff0000u); }
__device__ __forceinline__ float bf_round(float f) { return __bfloat162float(__float2bfloat16_rn(f)); }
__device__ __forceinline__ uint32_t bf_bits(float f) { return (uint32_t)__bfloat16_as_ushort(__float2bfloat16_rn(f)); }

__device__ __forceinline__ void accum(const uint4& v, float (&s)[8], uint32_t (&m)[4]) {
    s[0] += bf_lo(v.x); s[1] += bf_hi(v.x); m[0] = bf2_max(m[0], v.x);
    s[2] += bf_lo(v.y); s[3] += bf_hi(v.y); m[1] = bf2_max(m[1], v.y);
    s[4] += bf_lo(v.z); s[5] += bf_hi(v.z); m[2] = bf2_max(m[2], v.z);
    s[6] += bf_lo(v.w); s[7] += bf_hi(v.w); m[3] = bf2_max(m[3], v.w);
}
__device__ __forceinline__ uint4 scale4(const uint4& v, const uint4& sc) {
    uint4 o;
    o.x = bf2_mul(v.x, sc.x); o.y = bf2_mul(v.y, sc.y); o.z = bf2_mul(v.z, sc.z); o.w = bf2_mul(v.w, sc.w);
    return o;
}
#define PIN_ACC() asm volatile("" : "+f"(s[0]), "+f"(s[1]), "+f"(s[2]), "+f"(s[3]), "+f"(s[4]), "+f"(s[5]), "+f"(s[6]), "+f"(s[7]), \
                                    "+r"(m[0]), "+r"(m[1]), "+r"(m[2]), "+r"(m[3]))


__global__ void __launch_bounds__(NT, 1)
cbam_fused_kernel(const __grid_constant__ CUtensorMap tm, const __grid_constant__ CUtensorMap tm_rem,
                  const __nv_bfloat16* __restrict__ x,
                  const __nv_bfloat16* __restrict__ w1, const __nv_bfloat16* __restrict__ w2,
                  __nv_bfloat16* __restrict__ out, const int tau_ns, const int kmax)
{
    extern __shared__ __align__(1024) unsigned char smem[];
    const uint32_t sb = smem_u32(smem);
    const int tid = threadIdx.x, warp = tid >> 5, lane = tid & 31;
    const int g = blockIdx.x % NG, rg = blockIdx.x / NG;
    const uint32_t bar0 = sb + OFF_BAR;

    uint64_t pol;
    asm volatile("createpolicy.fractional.L2::evict_first.b64 %0, 1.0;" : "=l"(pol));

    const size_t tbase = (size_t)(rg * CROWS + (tid >> 3)) * 48 + g * 8 + (tid & 7);
    uint4 r[NREG * NP];
    {
        const uint4* xb = reinterpret_cast<const uint4*>(x) + tbase;
#pragma unroll
        for (int c = 0; c < NLDG; c++)
#pragma unroll
            for (int p = 0; p < NP; p++) r[c * NP + p] = ldg_stream(xb + (size_t)(c * NRG * CROWS + p * 32) * 48, pol);
    }
    const int rem_row0 = REM_BASE + (rg - 1) * REM_ROWS;
    const int rem_valid = (rg == 0) ? 0 : min(REM_ROWS, ROWS - rem_row0);
    auto issue = [&](int cn) {
        if (cn < NCHUNK) {
            const int slot = (cn < NLDG + NSLOT) ? cn - NLDG : cn - NLDG - NSLOT;
            mbar_expect_tx(bar0 + cn * 8, CBYTES);
            tma_load_2d(sb + OFF_SLOTS + slot * CBYTES, &tm, bar0 + cn * 8, g * 64, (cn * NRG + rg) * CROWS, pol);
        } else if (cn == NCHUNK && rg != 0) {
            mbar_expect_tx(bar0 + NCHUNK * 8, REM_ROWS * 128);
            tma_load_2d(sb + OFF_REM, &tm_rem, bar0 + NCHUNK * 8, g * 64, rem_row0, pol);
        }
    };

    int next = KINIT;
    const unsigned int t_start = gtime();
    auto pump = [&](int done) {
        while (next <= NCHUNK && next - done < kmax &&
               (next - done < KMIN || (int)(gtime() - t_start) >= (next - 1) * tau_ns)) { issue(next); next++; }
    };
    auto wait_chunk = [&](int c) {
        if (warp == 0) {
            int it = 0;
            while (!__all_sync(~0u, mbar_test(bar0 + c * 8, 0))) {
                if (lane == 0) pump(c);
                __syncwarp();
                if (++it > (SPIN_LIMIT << 4)) break;
            }
            if (lane == 0) pump(c + 1);
            __syncwarp();
        } else {
            mbar_wait(bar0 + c * 8, 0);
        }
    };

    if (warp == 0) {
        if (lane == 0) {
            asm volatile("prefetch.tensormap [%0];" ::"l"((uint64_t)&tm) : "memory");
            asm volatile("prefetch.tensormap [%0];" ::"l"((uint64_t)&tm_rem) : "memory");
        }
        if (lane < NCHUNK + 1) mbar_init(bar0 + lane * 8, 1);
        asm volatile("fence.mbarrier_init.release.cluster;" ::: "memory");
        __syncwarp();
        if (lane == 0) {
#pragma unroll 1
            for (int c = NLDG; c < KINIT; c++) issue(c);
        }
    }
    if (rg == 0) {
        const uint4* w1g = reinterpret_cast<const uint4*>(w1 + (size_t)g * 64 * HID);
#pragma unroll
        for (int i = 0; i < 3; i++) cp_async16(sb + OFF_W1 + (tid + i * NT) * 16, w1g + tid + i * NT);
    }
#pragma unroll
    for (int i = 0; i < 3; i++) {
        const int q = tid + i * NT;
        cp_async16(sb + OFF_W2 + ((q & ~7) | ((q ^ (q >> 4)) & 7)) * 16, w2 + (size_t)(q >> 3) * C_TOT + g * 64 + (q & 7) * 8);
    }
    asm volatile("cp.async.commit_group;" ::: "memory");
    unsigned int epoch;
    asm volatile("ld.relaxed.gpu.global.u32 %0, [%1];" : "=r"(epoch) : "l"(&g_epoch) : "memory");
    if (warp == 1) st_relaxed_2x64(&g_part[g][rg][lane], 0ull, 0ull);
    if (rg == 0 && tid >= 64) {
        const int j = (tid - 64) % HID, k = (tid - 64) / HID;
#pragma unroll
        for (int cp = 0; cp < NCOPY / 2; cp++) st_relaxed_2x32(&g_hpart[k * (NCOPY / 2) + cp][g][j], 0u, 0u);
    }
    __syncthreads();

    const uint32_t toff = tid * 16;
    float s[8];
    uint32_t m[4];
#pragma unroll
    for (int i = 0; i < 8; i++) s[i] = 0.f;
#pragma unroll
    for (int i = 0; i < 4; i++) m[i] = 0xff80ff80u;

#pragma unroll
    for (int c = 0; c < NLDG; c++) {
#pragma unroll
        for (int p = 0; p < NP; p++) accum(r[c * NP + p], s, m);
        PIN_ACC();
        if (tid == 0) pump(c + 1);
    }
#pragma unroll
    for (int c = NLDG; c < NREG; c++) {
        wait_chunk(c);
#pragma unroll
        for (int p = 0; p < NP; p++) r[c * NP + p] = lds128(sb + OFF_SLOTS + (c - NLDG) * CBYTES + p * 4096 + toff);
#pragma unroll
        for (int p = 0; p < NP; p++) accum(r[c * NP + p], s, m);
        PIN_ACC();
        __syncthreads();
    }
    asm volatile("cp.async.wait_all;" ::: "memory");
#pragma unroll 1
    for (int c = NREG; c < NCHUNK; c++) {
        const int slot = (c < NLDG + NSLOT) ? c - NLDG : c - NLDG - NSLOT;
        wait_chunk(c);
        uint4 v[NP];
#pragma unroll
        for (int p = 0; p < NP; p++) v[p] = lds128(sb + OFF_SLOTS + slot * CBYTES + p * 4096 + toff);
#pragma unroll
        for (int p = 0; p < NP; p++) accum(v[p], s, m);
    }
    if (rg != 0) {
        mbar_wait(bar0 + NCHUNK * 8, 0);
        const int r0 = tid >> 3;
        if (r0 < rem_valid) { uint4 v = lds128(sb + OFF_REM + toff); accum(v, s, m); }
        if (r0 + 32 < rem_valid) { uint4 v = lds128(sb + OFF_REM + 4096 + toff); accum(v, s, m); }
    }
    const uint32_t t16 = epoch % 65535u + 1u;
    const uint32_t t4 = epoch % 15u + 1u;

    {
        uint4* red = reinterpret_cast<uint4*>(smem + OFF_RED);
        const bool up = (lane & 16) != 0;
        float k0 = up ? s[4] : s[0], k1 = up ? s[5] : s[1], k2 = up ? s[6] : s[2], k3 = up ? s[7] : s[3];
        float t0 = up ? s[0] : s[4], t1 = up ? s[1] : s[5], t2 = up ? s[2] : s[6], t3 = up ? s[3] : s[7];
        uint32_t km0 = up ? m[2] : m[0], km1 = up ? m[3] : m[1];
        uint32_t tm0 = up ? m[0] : m[2], tm1 = up ? m[1] : m[3];
        k0 += __shfl_xor_sync(~0u, t0, 16); k1 += __shfl_xor_sync(~0u, t1, 16);
        k2 += __shfl_xor_sync(~0u, t2, 16); k3 += __shfl_xor_sync(~0u, t3, 16);
        km0 = bf2_max(km0, __shfl_xor_sync(~0u, tm0, 16));
        km1 = bf2_max(km1, __shfl_xor_sync(~0u, tm1, 16));
        const bool up2 = (lane & 8) != 0;
        float a0 = up2 ? k2 : k0, a1 = up2 ? k3 : k1;
        float b0 = up2 ? k0 : k2, b1 = up2 ? k1 : k3;
        uint32_t am = up2 ? km1 : km0, bm = up2 ? km0 : km1;
        a0 += __shfl_xor_sync(~0u, b0, 8); a1 += __shfl_xor_sync(~0u, b1, 8);
        am = bf2_max(am, __shfl_xor_sync(~0u, bm, 8));
        red[warp * 32 + lane] = make_uint4(__float_as_uint(a0), __float_as_uint(a1), am, 0u);
        __syncthreads();
        if (warp == 0) {
            uint4 v[8];
#pragma unroll
            for (int w = 0; w < 8; w++) v[w] = red[w * 32 + lane];
#define F_(a) __uint_as_float(a)
            a0 = ((F_(v[0].x) + F_(v[1].x)) + (F_(v[2].x) + F_(v[3].x))) + ((F_(v[4].x) + F_(v[5].x)) + (F_(v[6].x) + F_(v[7].x)));
            a1 = ((F_(v[0].y) + F_(v[1].y)) + (F_(v[2].y) + F_(v[3].y))) + ((F_(v[4].y) + F_(v[5].y)) + (F_(v[6].y) + F_(v[7].y)));
            am = bf2_max(bf2_max(bf2_max(v[0].z, v[1].z), bf2_max(v[2].z, v[3].z)), bf2_max(bf2_max(v[4].z, v[5].z), bf2_max(v[6].z, v[7].z)));
            const unsigned long long p0 = ((unsigned long long)((t16 << 16) | (am & 0xffffu)) << 32) | __float_as_uint(a0);
            const unsigned long long p1 = ((unsigned long long)((t16 << 16) | (am >> 16)) << 32) | __float_as_uint(a1);
            st_relaxed_2x64(&g_part[g][rg][(lane & 7) * 4 + (lane >> 3)], p0, p1);
        }
    }

    if (rg == 0) {
        const int p = lane & 3, rs = lane >> 2;
        float w1f[8][3];
        {
            const __nv_bfloat16* w1s = reinterpret_cast<const __nv_bfloat16*>(smem + OFF_W1);
#pragma unroll
            for (int c = 0; c < 8; c++)
#pragma unroll
                for (int u = 0; u < 3; u++) w1f[c][u] = __bfloat162float(w1s[(warp * 8 + c) * HID + lane + 32 * u]);
        }
        float s0, s1; uint32_t mm;
        {
            ulonglong2 v0 = make_ulonglong2(0ull, 0ull), v1 = v0, v2 = v0;
            const ulonglong2* src = &g_part[g][rs][warp * 4 + p];
            const bool has3 = (rs + 16) < NRG;
            uint32_t n0 = 1u, n1 = 1u, n2 = has3;
            int it = 0;
            while (true) {
                ldp_2x64(v0, src, n0);
                ldp_2x64(v1, src + 8 * 32, n1);
                ldp_2x64(v2, src + 16 * 32, n2);
                if (((uint32_t)(v0.x >> 48) == t16) && ((uint32_t)(v0.y >> 48) == t16)) n0 = 0;
                if (((uint32_t)(v1.x >> 48) == t16) && ((uint32_t)(v1.y >> 48) == t16)) n1 = 0;
                if (((uint32_t)(v2.x >> 48) == t16) && ((uint32_t)(v2.y >> 48) == t16)) n2 = 0;
                if ((n0 | n1 | n2) == 0u || ++it > SPIN_LIMIT) break;
            }
            s0 = __uint_as_float((uint32_t)v0.x) + __uint_as_float((uint32_t)v1.x);
            s1 = __uint_as_float((uint32_t)v0.y) + __uint_as_float((uint32_t)v1.y);
            mm = bf2_max(((uint32_t)(v0.x >> 32) & 0xffffu) | ((uint32_t)(v0.y >> 32) << 16),
                         ((uint32_t)(v1.x >> 32) & 0xffffu) | ((uint32_t)(v1.y >> 32) << 16));
            if (has3) {
                s0 += __uint_as_float((uint32_t)v2.x); s1 += __uint_as_float((uint32_t)v2.y);
                mm = bf2_max(mm, ((uint32_t)(v2.x >> 32) & 0xffffu) | ((uint32_t)(v2.y >> 32) << 16));
            }
        }
        __syncwarp();
#pragma unroll
        for (int o = 4; o <= 16; o <<= 1) {
            s0 += __shfl_xor_sync(~0u, s0, o);
            s1 += __shfl_xor_sync(~0u, s1, o);
            mm = bf2_max(mm, __shfl_xor_sync(~0u, mm, o));
        }
        const uint32_t gp = bf_bits(s0 * (1.0f / ROWS)) | (bf_bits(s1 * (1.0f / ROWS)) << 16);
        float ha[3] = {0.f, 0.f, 0.f}, hm[3] = {0.f, 0.f, 0.f};
#pragma unroll
        for (int q = 0; q < 4; q++) {
            const uint32_t gq = __shfl_sync(~0u, gp, q);
            const uint32_t mq = __shfl_sync(~0u, mm, q);
            const float g0 = bf_lo(gq), g1 = bf_hi(gq), m0 = bf_lo(mq), m1 = bf_hi(mq);
#pragma unroll
            for (int u = 0; u < 3; u++) {
                ha[u] = fmaf(g0, w1f[2 * q][u], ha[u]); ha[u] = fmaf(g1, w1f[2 * q + 1][u], ha[u]);
                hm[u] = fmaf(m0, w1f[2 * q][u], hm[u]); hm[u] = fmaf(m1, w1f[2 * q + 1][u], hm[u]);
            }
        }
        float2* red2 = reinterpret_cast<float2*>(smem + OFF_REM);
#pragma unroll
        for (int u = 0; u < 3; u++) red2[warp * HID + lane + 32 * u] = make_float2(ha[u], hm[u]);
        __syncthreads();
        if (tid < 2 * HID) {
            const int j = tid % HID, k = tid / HID;
            float2 v[8];
#pragma unroll
            for (int w = 0; w < 8; w++) v[w] = red2[w * HID + j];
            const float a = ((v[0].x + v[1].x) + (v[2].x + v[3].x)) + ((v[4].x + v[5].x) + (v[6].x + v[7].x));
            const float b = ((v[0].y + v[1].y) + (v[2].y + v[3].y)) + ((v[4].y + v[5].y) + (v[6].y + v[7].y));
            const uint32_t pa = (__float_as_uint(a) & ~15u) | t4;
            const uint32_t pb = (__float_as_uint(b) & ~15u) | t4;
#pragma unroll
            for (int cp = 0; cp < NCOPY / 2; cp++) st_relaxed_2x32(&g_hpart[k * (NCOPY / 2) + cp][g][j], pa, pb);
        }
    }

    uint4 sc;
    {
        float2* hs = reinterpret_cast<float2*>(smem + OFF_W1);
        const int cp = lane & 3, js = lane >> 2;
        float w2f[12][2];
        {
            const uint32_t* w2s = reinterpret_cast<const uint32_t*>(smem + OFF_W2);
#pragma unroll
            for (int i = 0; i < 12; i++) {
                const uint32_t w = w2s[((i >> 1) * 16 + js * 2 + (i & 1)) * 32 + (warp ^ js) * 4 + cp];
                w2f[i][0] = bf_lo(w); w2f[i][1] = bf_hi(w);
            }
        }
        if (tid < HID) {
            const uint2* src = &g_hpart[blockIdx.x % NCOPY][0][tid];
            uint2 v[NG];
#pragma unroll
            for (int q = 0; q < NG; q++) v[q] = make_uint2(0u, 0u);
            uint32_t need = (1u << NG) - 1u;
            int it = 0;
            while (true) {
#pragma unroll
                for (int q = 0; q < NG; q++) ldp_2x32(v[q], src + q * HID, (need >> q) & 1u);
#pragma unroll
                for (int q = 0; q < NG; q++)
                    if (((v[q].x & 15u) == t4) && ((v[q].y & 15u) == t4)) need &= ~(1u << q);
                if (need == 0u || ++it > SPIN_LIMIT) break;
            }
#define G_(a) __uint_as_float((a) & ~15u)
            float a = ((G_(v[0].x) + G_(v[1].x)) + (G_(v[2].x) + G_(v[3].x))) + (G_(v[4].x) + G_(v[5].x));
            float b = ((G_(v[0].y) + G_(v[1].y)) + (G_(v[2].y) + G_(v[3].y))) + (G_(v[4].y) + G_(v[5].y));
            a = bf_round(a); b = bf_round(b);
            a = a * (a > 0.f ? 1.f : 0.f);
            b = b * (b > 0.f ? 1.f : 0.f);
            hs[tid] = make_float2(a, b);
        }
        __syncthreads();
        float za0 = 0.f, za1 = 0.f, zm0 = 0.f, zm1 = 0.f;
        const float4* hs4 = reinterpret_cast<const float4*>(hs);
#pragma unroll
        for (int i = 0; i < 6; i++) {
            const float4 h = hs4[i * 8 + js];
            za0 = fmaf(h.x, w2f[2 * i][0], za0); za1 = fmaf(h.x, w2f[2 * i][1], za1);
            zm0 = fmaf(h.y, w2f[2 * i][0], zm0); zm1 = fmaf(h.y, w2f[2 * i][1], zm1);
            za0 = fmaf(h.z, w2f[2 * i + 1][0], za0); za1 = fmaf(h.z, w2f[2 * i + 1][1], za1);
            zm0 = fmaf(h.w, w2f[2 * i + 1][0], zm0); zm1 = fmaf(h.w, w2f[2 * i + 1][1], zm1);
        }
        const bool up = (lane & 4) != 0;
        float ka = up ? za1 : za0, km = up ? zm1 : zm0;
        const float ta = up ? za0 : za1, tmm = up ? zm0 : zm1;
        ka += __shfl_xor_sync(~0u, ta, 4); km += __shfl_xor_sync(~0u, tmm, 4);
        ka += __shfl_xor_sync(~0u, ka, 8); km += __shfl_xor_sync(~0u, km, 8);
        ka += __shfl_xor_sync(~0u, ka, 16); km += __shfl_xor_sync(~0u, km, 16);
        if (lane < 8) {
            const float z = bf_round(bf_round(ka) + bf_round(km));
            const float sg = __fdividef(1.0f, 1.0f + __expf(-z));
            __nv_bfloat16* scp = reinterpret_cast<__nv_bfloat16*>(smem + OFF_SCALE);
            scp[warp * 8 + (lane & 3) * 2 + (lane >> 2)] = __float2bfloat16_rn(sg);
        }
        __syncthreads();
        sc = lds128(sb + OFF_SCALE + (lane & 7) * 16);
    }

    uint4* ob = reinterpret_cast<uint4*>(out) + tbase;
#pragma unroll
    for (int c = 0; c < NREG; c++)
#pragma unroll
        for (int p = 0; p < NP; p++)
            stg_stream(ob + (size_t)(c * NRG * CROWS + p * 32) * 48, scale4(r[c * NP + p], sc), pol);
    if (blockIdx.x == 0 && tid == 0) {
        asm volatile("st.relaxed.gpu.global.u32 [%0], %1;" ::"l"(&g_epoch), "r"(epoch + 1u) : "memory");
    }
#pragma unroll 1
    for (int c = NREG; c < NCHUNK; c++) {
        const int slot = (c < NLDG + NSLOT) ? c - NLDG : c - NLDG - NSLOT;
        uint4 v[NP];
#pragma unroll
        for (int p = 0; p < NP; p++) v[p] = lds128(sb + OFF_SLOTS + slot * CBYTES + p * 4096 + toff);
#pragma unroll
        for (int p = 0; p < NP; p++) stg_stream(ob + (size_t)(c * NRG * CROWS + p * 32) * 48, scale4(v[p], sc), pol);
    }
    {
        const int r0 = tid >> 3;
        uint4* orem = reinterpret_cast<uint4*>(out) + (size_t)(rem_row0 + r0) * 48 + g * 8 + (tid & 7);
        if (r0 < rem_valid) { uint4 v = lds128(sb + OFF_REM + toff); stg_stream(orem, scale4(v, sc), pol); }
        if (r0 + 32 < rem_valid) { uint4 v = lds128(sb + OFF_REM + 4096 + toff); stg_stream(orem + 32 * 48, scale4(v, sc), pol); }
    }
}

__global__ void fb_pool_kernel(const __nv_bfloat16* __restrict__ x) {
    const int c = threadIdx.x;
    float s = 0.f; float mx = -INFINITY;
    const __nv_bfloat16* p = x + (size_t)blockIdx.x * 256 * C_TOT + c;
    bool nan = false;
    for (int r = 0; r < 256; r++) { float v = __bfloat162float(p[(size_t)r * C_TOT]); s += v; mx = fmaxf(mx, v); nan |= (v != v); }
    if (nan) mx = __int_as_float(0x7fffffff);
    g_fb_sum[blockIdx.x][c] = s; g_fb_max[blockIdx.x][c] = mx;
}
__global__ void fb_mlp_kernel(const __nv_bfloat16* __restrict__ w1, const __nv_bfloat16* __restrict__ w2) {
    __shared__ float ga[C_TOT], gm[C_TOT], ha[HID], hm[HID];
    const int c = threadIdx.x;
    float s = 0.f, mx = -INFINITY; bool nan = false;
    for (int b = 0; b < 256; b++) { s += g_fb_sum[b][c]; float v = g_fb_max[b][c]; mx = fmaxf(mx, v); nan |= (v != v); }
    if (nan) mx = __int_as_float(0x7fffffff);
    ga[c] = bf_round(s * (1.0f / ROWS)); gm[c] = mx;
    __syncthreads();
    if (c < HID) {
        float a = 0.f, b = 0.f;
        for (int k = 0; k < C_TOT; k++) { float w = __bfloat162float(w1[k * HID + c]); a = fmaf(ga[k], w, a); b = fmaf(gm[k], w, b); }
        a = bf_round(a); b = bf_round(b);
        ha[c] = a * (a > 0.f ? 1.f : 0.f); hm[c] = b * (b > 0.f ? 1.f : 0.f);
    }
    __syncthreads();
    float a = 0.f, b = 0.f;
    for (int j = 0; j < HID; j++) { float w = __bfloat162float(w2[j * C_TOT + c]); a = fmaf(ha[j], w, a); b = fmaf(hm[j], w, b); }
    const float z = bf_round(bf_round(a) + bf_round(b));
    g_fb_scale[c] = __float2bfloat16_rn(1.0f / (1.0f + __expf(-z)));
}
__global__ void fb_scale_kernel(const uint4* __restrict__ x, uint4* __restrict__ out) {
    const size_t n = (size_t)ROWS * 48;
    for (size_t i = blockIdx.x * (size_t)blockDim.x + threadIdx.x; i < n; i += (size_t)gridDim.x * blockDim.x) {
        const uint4 sc = reinterpret_cast<const uint4*>(g_fb_scale)[i % 48];
        out[i] = scale4(x[i], sc);
    }
}

typedef CUresult (*PFN_encodeTiled)(CUtensorMap*, CUtensorMapDataType, cuuint32_t, void*, const cuuint64_t*,
                                    const cuuint64_t*, const cuuint32_t*, const cuuint32_t*, CUtensorMapInterleave,
                                    CUtensorMapSwizzle, CUtensorMapL2promotion, CUtensorMapFloatOOBfill);

}

extern "C" void kernel_launch(void* const* d_in, const int* in_sizes, int n_in, void* d_out, int out_size) {
    const __nv_bfloat16* x  = (const __nv_bfloat16*)d_in[0];
    const __nv_bfloat16* w1 = (const __nv_bfloat16*)d_in[1];
    const __nv_bfloat16* w2 = (const __nv_bfloat16*)d_in[2];
    __nv_bfloat16* out = (__nv_bfloat16*)d_out;
    cudaStream_t stream = cudaStreamPerThread;

    static int mode = -1;
    static PFN_encodeTiled enc = nullptr;
    static int tau_ns = 0, kmax = 4;
    if (mode < 0) {
        mode = 0;
        int dev = 0, sms = 0, occ = 0, coop = 0;
        cudaGetDevice(&dev);
        cudaDeviceGetAttribute(&sms, cudaDevAttrMultiProcessorCount, dev);
        cudaDeviceGetAttribute(&coop, cudaDevAttrCooperativeLaunch, dev);
        void* fn = nullptr;
        cudaDriverEntryPointQueryResult qr;
        if (cudaGetDriverEntryPoint("cuTensorMapEncodeTiled", &fn, cudaEnableDefault, &qr) == cudaSuccess && fn &&
            cudaFuncSetAttribute(cbam_fused_kernel, cudaFuncAttributeMaxDynamicSharedMemorySize, SMEM_BYTES) == cudaSuccess &&
            cudaOccupancyMaxActiveBlocksPerMultiprocessor(&occ, cbam_fused_kernel, NT, SMEM_BYTES) == cudaSuccess &&
            coop && occ >= 1 && sms * occ >= NBLK) {
            enc = (PFN_encodeTiled)fn;
            mode = 1;
            int mclk_khz = 0, bus_bits = 0;
            if (cudaDeviceGetAttribute(&mclk_khz, cudaDevAttrMemoryClockRate, dev) == cudaSuccess &&
                cudaDeviceGetAttribute(&bus_bits, cudaDevAttrGlobalMemoryBusWidth, dev) == cudaSuccess &&
                mclk_khz > 0 && bus_bits > 0) {
                const double bytes_per_ns = 2.0 * mclk_khz * 1e-6 * (bus_bits / 8.0);
                tau_ns = (int)(1.03 * (double)CBYTES * NBLK / bytes_per_ns);
                kmax = KMAX;
            }
        }
        (void)cudaGetLastError();
    }
    if (mode == 1) {
        CUtensorMap tm, tmr;
        cuuint64_t gd[2] = {(cuuint64_t)C_TOT, (cuuint64_t)ROWS};
        cuuint64_t gs[1] = {(cuuint64_t)C_TOT * 2};
        cuuint32_t box[2] = {64, (cuuint32_t)CROWS};
        cuuint32_t boxr[2] = {64, (cuuint32_t)REM_ROWS};
        cuuint32_t es[2] = {1, 1};
        CUresult r1 = enc(&tm, CU_TENSOR_MAP_DATA_TYPE_BFLOAT16, 2, (void*)x, gd, gs, box, es, CU_TENSOR_MAP_INTERLEAVE_NONE,
                          CU_TENSOR_MAP_SWIZZLE_NONE, CU_TENSOR_MAP_L2_PROMOTION_L2_128B, CU_TENSOR_MAP_FLOAT_OOB_FILL_NONE);
        CUresult r2 = enc(&tmr, CU_TENSOR_MAP_DATA_TYPE_BFLOAT16, 2, (void*)x, gd, gs, boxr, es, CU_TENSOR_MAP_INTERLEAVE_NONE,
                          CU_TENSOR_MAP_SWIZZLE_NONE, CU_TENSOR_MAP_L2_PROMOTION_L2_128B, CU_TENSOR_MAP_FLOAT_OOB_FILL_NONE);
        if (r1 == CUDA_SUCCESS && r2 == CUDA_SUCCESS) {
            cudaLaunchConfig_t cfg = {};
            cfg.gridDim = dim3(NBLK); cfg.blockDim = dim3(NT); cfg.dynamicSmemBytes = SMEM_BYTES; cfg.stream = stream;
            cudaLaunchAttribute at[1];
            at[0].id = cudaLaunchAttributeCooperative; at[0].val.cooperative = 1;
            cfg.attrs = at; cfg.numAttrs = 1;
            if (cudaLaunchKernelEx(&cfg, cbam_fused_kernel, tm, tmr, x, w1, w2, out, tau_ns, kmax) == cudaSuccess) return;
            (void)cudaGetLastError();
        }
    }
    fb_pool_kernel<<<256, C_TOT, 0, stream>>>(x);
    fb_mlp_kernel<<<1, C_TOT, 0, stream>>>(w1, w2);
    fb_scale_kernel<<<1056, 256, 0, stream>>>((const uint4*)x, (uint4*)out);
}
```
